```python
import torch

def _softmax(x, axis=-1):
    return torch.softmax(x, dim=axis)
def _gelu(x):
    return torch.nn.functional.gelu(x, approximate="tanh")
def _silu(x):
    return torch.nn.functional.silu(x)
def _sigmoid(x):
    return torch.sigmoid(x)
def _layernorm(x, axis=-1, eps=1e-5):
    m = x.mean(dim=axis, keepdim=True)
    v = x.var(dim=axis, keepdim=True, unbiased=False)
    return (x - m) / torch.sqrt(v + eps)
def _scatter_add(tgt, idx, src, axis=0):
    return tgt.clone().index_add_(axis, idx, src)
def _segment_sum(src, seg, n):
    out = torch.zeros((n,) + src.shape[1:], dtype=src.dtype)
    return out.index_add_(0, seg, src)
def _pad(x, pw):
    flat = tuple(v for pair in reversed(pw) for v in pair)
    return torch.nn.functional.pad(x, flat)

kernel_name = 'gated_mix__linear_attn_block__linear_attn_block__prompt'

def setup_inputs():

    _w = (lambda a: (lambda t: t.to(torch.bfloat16) if t.is_floating_point() else t)(torch.as_tensor(a)))
    def _A_setup():
        B, S, D = 1, 2048, 512
        return {
            "x": _w((lambda *s: torch.randn(*s, dtype=torch.bfloat16) * 0.05)(B, S, D)),
            "wqkv": _w((lambda *s: torch.randn(*s, dtype=torch.bfloat16) * 0.8)(D, 3 * D)),
            "wo": _w((lambda *s: torch.randn(*s, dtype=torch.bfloat16) * 0.05)(D, D)),
        }
    _A_in = _A_setup()

    def _B_setup():
        B, S, D = 1, 2048, 512
        return {
            "x": _w((lambda *s: torch.randn(*s, dtype=torch.bfloat16) * 0.05)(B, S, D)),
            "wqkv": _w((lambda *s: torch.randn(*s, dtype=torch.bfloat16) * 0.8)(D, 3 * D)),
            "wo": _w((lambda *s: torch.randn(*s, dtype=torch.bfloat16) * 0.05)(D, D)),
        }
    _B_in = _B_setup()

    return {
        "A_x": _A_in["x"],
        "A_wqkv": _A_in["wqkv"],
        "A_wo": _A_in["wo"],
        "B_x": _B_in["x"],
        "B_wqkv": _B_in["wqkv"],
        "B_wo": _B_in["wo"],
        "gate_w": _w((lambda *s: torch.randn(*s, dtype=torch.bfloat16) * 0.05)(512) * 16.0),
    }

def reference(A_x, A_wqkv, A_wo, B_x, B_wqkv, B_wo, gate_w):
    def _A_ref(x, wqkv, wo):
        B, S, D = x.shape
        H = 32; Dh = D // H
        qkv = (lambda x, *d: x.permute(*d))((x @ wqkv).reshape(B, S, 3, H, Dh), 2, 0, 3, 1, 4)
        q, k, v = qkv[0], qkv[1], qkv[2]
        phi = lambda t: torch.where(t > 0, t + 1, torch.exp(t)) + 1e-6
        pq, pk = phi(q), phi(k)
        kv = torch.einsum("bhsd,bhse->bhde", pk, v)
        z = torch.einsum("bhsd->bhd", pk)
        num = torch.einsum("bhqd,bhde->bhqe", pq, kv)
        den = torch.einsum("bhqd,bhd->bhq", pq, z)[..., None] + 1e-6
        o = num / den
        return (lambda x, *d: x.permute(*d))(o, 0, 2, 1, 3).reshape(B, S, D) @ wo

    def _B_ref(x, wqkv, wo):
        B, S, D = x.shape
        H = 32; Dh = D // H
        qkv = (lambda x, *d: x.permute(*d))((x @ wqkv).reshape(B, S, 3, H, Dh), 2, 0, 3, 1, 4)
        q, k, v = qkv[0], qkv[1], qkv[2]
        phi = lambda t: torch.where(t > 0, t + 1, torch.exp(t)) + 1e-6
        pq, pk = phi(q), phi(k)
        kv = torch.einsum("bhsd,bhse->bhde", pk, v)
        z = torch.einsum("bhsd->bhd", pk)
        num = torch.einsum("bhqd,bhde->bhqe", pq, kv)
        den = torch.einsum("bhqd,bhd->bhq", pq, z)[..., None] + 1e-6
        o = num / den
        return (lambda x, *d: x.permute(*d))(o, 0, 2, 1, 3).reshape(B, S, D) @ wo

    x = A_x
    g = _sigmoid((x * gate_w).sum(-1, keepdims=True))
    a = _A_ref(x, A_wqkv, A_wo)
    b = _B_ref(x, B_wqkv, B_wo)
    return g * a + (1 - g) * b
```

```cpp
#include <cuda_runtime.h>
#include <cuda.h>
#include <cuda_bf16.h>
#include <stdint.h>

#define TRACE 0

#define PREFETCH0 1
#define PROMO CU_TENSOR_MAP_L2_PROMOTION_L2_256B
#define QSKEW 3
#define TAIL 1
#define PREFIX 5
#define BSPLIT 1
#define NLO 9
#define VPIN 1
#define NSTG 4
#define SCHED_LD {0, 2, 4, 6, 8, 10, 12, 12, 12, 12, 12, 12, 12, 12, 12, 15, 18, 21, 24, 24, 24, 24, 24, 24, 24}
#define SCHED_ST {0, 0, 0, 4, 5, 6, 7}
#define HIDEFER 1
#define MAPPING 1

namespace {

constexpr int kThreads = 384;
constexpr uint32_t UNIT = 16384, RING = 8;
constexpr uint32_t BAR_OFF = 14 * UNIT;
constexpr uint32_t KVS_OFF = 0;
constexpr uint32_t ZS_OFF = 4096;
constexpr uint32_t GS_OFF = 8192;
constexpr uint32_t TAG_OFF = BAR_OFF + 248;
constexpr uint32_t SMEM_BYTES = BAR_OFF + 256 + (TRACE ? 384 : 0);
constexpr int B_XFULL = 0, B_FULL = 8, B_EMPTY = 14, B_WO = 20, B_E1 = 21, B_XFREE = 22, B_CLR = 23, B_KVFULL = 24,
              B_EPOCH = 25, B_PFREE = 26, B_PIN = 27;
constexpr int kSpin = 1 << 20;

struct __align__(64) Params {
  CUtensorMap x, out, w[2], wo[2];
};
struct Ptrs {
  const void* wqkv[2];
  const void* wo[2];
  uint4* out;
};

__device__ unsigned g_clean[128 * 8];
__device__ uint4 g_logit[2048][2];
__device__ uint4 g_part[8][16][2][16][18];
__device__ uint4 g_fin[8][3][8][32];
__device__ uint4 g_obuf[16][2][2][32][128];
#define TR(slot)
#define TRW(slot)
#define TRD(slot, code) code

__device__ __forceinline__ void mbar_init(uint32_t bar, uint32_t cnt) {
  asm volatile("mbarrier.init.shared::cta.b64 [%0], %1;" ::"r"(bar), "r"(cnt) : "memory");
}
__device__ __forceinline__ void mbar_expect_tx(uint32_t bar, uint32_t bytes) {
  asm volatile("mbarrier.arrive.expect_tx.shared::cta.b64 _, [%0], %1;" ::"r"(bar), "r"(bytes) : "memory");
}
__device__ __forceinline__ void mbar_arrive(uint32_t bar) {
  asm volatile("mbarrier.arrive.shared::cta.b64 _, [%0];" ::"r"(bar) : "memory");
}
__device__ __forceinline__ void mbar_wait(uint32_t bar, uint32_t par) {
  asm volatile(
      "{ .reg .pred p; .reg .u32 n; mov.u32 n, 0;\n"
      "W: mbarrier.try_wait.parity.shared::cta.b64 p, [%0], %1;\n"
      "add.u32 n, n, 1; setp.lt.and.u32 p, n, %2, !p; @p bra W; }" ::"r"(bar), "r"(par), "n"(kSpin) : "memory");
}
__device__ __forceinline__ void tma2d(uint32_t dst, const CUtensorMap* m, int c0, int c1, uint32_t bar) {
  asm volatile("cp.async.bulk.tensor.2d.shared::cluster.global.mbarrier::complete_tx::bytes [%0], [%1, {%3, %4}], [%2];"
               ::"r"(dst), "l"(m), "r"(bar), "r"(c0), "r"(c1) : "memory");
}
__device__ __forceinline__ void tma3d(uint32_t dst, const CUtensorMap* m, int c0, int c1, int c2, uint32_t bar) {
  asm volatile("cp.async.bulk.tensor.3d.shared::cluster.global.mbarrier::complete_tx::bytes [%0], [%1, {%3, %4, %5}], [%2];"
               ::"r"(dst), "l"(m), "r"(bar), "r"(c0), "r"(c1), "r"(c2) : "memory");
}
__device__ __forceinline__ void bar_sync(int id, int n) { asm volatile("bar.sync %0, %1;" ::"r"(id), "r"(n) : "memory"); }
#define WG_FENCE() asm volatile("wgmma.fence.sync.aligned;" ::: "memory")
#define WG_COMMIT() asm volatile("wgmma.commit_group.sync.aligned;" ::: "memory")
#define WG_WAIT(n) asm volatile("wgmma.wait_group.sync.aligned %0;" ::"n"(n) : "memory")
__device__ __forceinline__ uint64_t mkdesc(uint32_t addr) {
  return (uint64_t)((addr & 0x3FFFF) >> 4) | ((uint64_t)(8192 >> 4) << 16) | ((uint64_t)(1024 >> 4) << 32) | (1ull << 62);
}
#define SEQ() asm volatile("bar.warp.sync 0xffffffff;" ::: "memory")
template <int N>
__device__ __forceinline__ void reg_fence(float (&d)[N]) {
#pragma unroll
  for (int i = 0; i < N; i++) asm volatile("" : "+f"(d[i])::"memory");
}
__device__ __forceinline__ void wg_t(float (&d)[64], uint64_t da, uint64_t db, int sd) {
  asm volatile("{ .reg .pred p; setp.ne.b32 p, %66, 0;\n"
    "wgmma.mma_async.sync.aligned.m64n128k16.f32.bf16.bf16 {%0,%1,%2,%3,%4,%5,%6,%7,%8,%9,%10,%11,%12,%13,%14,%15,%16,%17,%18,%19,%20,%21,%22,%23,%24,%25,%26,%27,%28,%29,%30,%31,%32,%33,%34,%35,%36,%37,%38,%39,%40,%41,%42,%43,%44,%45,%46,%47,%48,%49,%50,%51,%52,%53,%54,%55,%56,%57,%58,%59,%60,%61,%62,%63}, %64, %65, p, 1, 1, 1, 0; }"
    : "+f"(d[0]), "+f"(d[1]), "+f"(d[2]), "+f"(d[3]), "+f"(d[4]), "+f"(d[5]), "+f"(d[6]), "+f"(d[7]),
      "+f"(d[8]), "+f"(d[9]), "+f"(d[10]), "+f"(d[11]), "+f"(d[12]), "+f"(d[13]), "+f"(d[14]), "+f"(d[15]),
      "+f"(d[16]), "+f"(d[17]), "+f"(d[18]), "+f"(d[19]), "+f"(d[20]), "+f"(d[21]), "+f"(d[22]), "+f"(d[23]),
      "+f"(d[24]), "+f"(d[25]), "+f"(d[26]), "+f"(d[27]), "+f"(d[28]), "+f"(d[29]), "+f"(d[30]), "+f"(d[31]),
      "+f"(d[32]), "+f"(d[33]), "+f"(d[34]), "+f"(d[35]), "+f"(d[36]), "+f"(d[37]), "+f"(d[38]), "+f"(d[39]),
      "+f"(d[40]), "+f"(d[41]), "+f"(d[42]), "+f"(d[43]), "+f"(d[44]), "+f"(d[45]), "+f"(d[46]), "+f"(d[47]),
      "+f"(d[48]), "+f"(d[49]), "+f"(d[50]), "+f"(d[51]), "+f"(d[52]), "+f"(d[53]), "+f"(d[54]), "+f"(d[55]),
      "+f"(d[56]), "+f"(d[57]), "+f"(d[58]), "+f"(d[59]), "+f"(d[60]), "+f"(d[61]), "+f"(d[62]), "+f"(d[63])
    : "l"(da), "l"(db), "r"(sd));
}
__device__ __forceinline__ void wg_q(float (&d)[64], uint64_t da, uint64_t db, int sd) {
  asm volatile("{ .reg .pred p; setp.ne.b32 p, %66, 0;\n"
    "wgmma.mma_async.sync.aligned.m64n128k16.f32.bf16.bf16 {%0,%1,%2,%3,%4,%5,%6,%7,%8,%9,%10,%11,%12,%13,%14,%15,%16,%17,%18,%19,%20,%21,%22,%23,%24,%25,%26,%27,%28,%29,%30,%31,%32,%33,%34,%35,%36,%37,%38,%39,%40,%41,%42,%43,%44,%45,%46,%47,%48,%49,%50,%51,%52,%53,%54,%55,%56,%57,%58,%59,%60,%61,%62,%63}, %64, %65, p, 1, 1, 0, 1; }"
    : "+f"(d[0]), "+f"(d[1]), "+f"(d[2]), "+f"(d[3]), "+f"(d[4]), "+f"(d[5]), "+f"(d[6]), "+f"(d[7]),
      "+f"(d[8]), "+f"(d[9]), "+f"(d[10]), "+f"(d[11]), "+f"(d[12]), "+f"(d[13]), "+f"(d[14]), "+f"(d[15]),
      "+f"(d[16]), "+f"(d[17]), "+f"(d[18]), "+f"(d[19]), "+f"(d[20]), "+f"(d[21]), "+f"(d[22]), "+f"(d[23]),
      "+f"(d[24]), "+f"(d[25]), "+f"(d[26]), "+f"(d[27]), "+f"(d[28]), "+f"(d[29]), "+f"(d[30]), "+f"(d[31]),
      "+f"(d[32]), "+f"(d[33]), "+f"(d[34]), "+f"(d[35]), "+f"(d[36]), "+f"(d[37]), "+f"(d[38]), "+f"(d[39]),
      "+f"(d[40]), "+f"(d[41]), "+f"(d[42]), "+f"(d[43]), "+f"(d[44]), "+f"(d[45]), "+f"(d[46]), "+f"(d[47]),
      "+f"(d[48]), "+f"(d[49]), "+f"(d[50]), "+f"(d[51]), "+f"(d[52]), "+f"(d[53]), "+f"(d[54]), "+f"(d[55]),
      "+f"(d[56]), "+f"(d[57]), "+f"(d[58]), "+f"(d[59]), "+f"(d[60]), "+f"(d[61]), "+f"(d[62]), "+f"(d[63])
    : "l"(da), "l"(db), "r"(sd));
}
__device__ __forceinline__ void wg_o64(float (&d)[32], const uint4& a, uint64_t db, int sd) {
  asm volatile("{ .reg .pred p; setp.ne.b32 p, %37, 0;\n"
    "wgmma.mma_async.sync.aligned.m64n64k16.f32.bf16.bf16 {%0,%1,%2,%3,%4,%5,%6,%7,%8,%9,%10,%11,%12,%13,%14,%15,%16,%17,%18,%19,%20,%21,%22,%23,%24,%25,%26,%27,%28,%29,%30,%31}, {%32,%33,%34,%35}, %36, p, 1, 1, 1; }"
    : "+f"(d[0]), "+f"(d[1]), "+f"(d[2]), "+f"(d[3]), "+f"(d[4]), "+f"(d[5]), "+f"(d[6]), "+f"(d[7]),
      "+f"(d[8]), "+f"(d[9]), "+f"(d[10]), "+f"(d[11]), "+f"(d[12]), "+f"(d[13]), "+f"(d[14]), "+f"(d[15]),
      "+f"(d[16]), "+f"(d[17]), "+f"(d[18]), "+f"(d[19]), "+f"(d[20]), "+f"(d[21]), "+f"(d[22]), "+f"(d[23]),
      "+f"(d[24]), "+f"(d[25]), "+f"(d[26]), "+f"(d[27]), "+f"(d[28]), "+f"(d[29]), "+f"(d[30]), "+f"(d[31])
    : "r"(a.x), "r"(a.y), "r"(a.z), "r"(a.w), "l"(db), "r"(sd));
}
__device__ __forceinline__ void poll_o_a(uint4 (&f)[24], const uint4* p0, const uint4* p1, const uint4* p2) {
  asm volatile("{ .reg .pred q; .reg .u32 n, m; mov.u32 n, 0;\n"
    "bra.uni C;\n"
    "L:\n"
    "ld.relaxed.gpu.global.v4.u32 {%0,%1,%2,%3}, [%24+0];\n"
    "ld.relaxed.gpu.global.v4.u32 {%4,%5,%6,%7}, [%25+0];\n"
    "ld.relaxed.gpu.global.v4.u32 {%8,%9,%10,%11}, [%26+0];\n"
    "ld.relaxed.gpu.global.v4.u32 {%12,%13,%14,%15}, [%24+2048];\n"
    "ld.relaxed.gpu.global.v4.u32 {%16,%17,%18,%19}, [%25+2048];\n"
    "ld.relaxed.gpu.global.v4.u32 {%20,%21,%22,%23}, [%26+2048];\n"
    "C: mov.u32 m, %%clock; or.b32 m, m, 1; min.u32 m, m, %0; min.u32 m, m, %4; min.u32 m, m, %8; min.u32 m, m, %12; min.u32 m, m, %16; min.u32 m, m, %20;\n"
    "setp.eq.u32 q, m, 0; vote.sync.any.pred q, q, 0xffffffff; add.u32 n, n, 1;\n"
    "setp.lt.and.u32 q, n, %27, q; @q bra.uni L; }"
    : "+r"(f[0].x), "+r"(f[0].y), "+r"(f[0].z), "+r"(f[0].w),
      "+r"(f[1].x), "+r"(f[1].y), "+r"(f[1].z), "+r"(f[1].w),
      "+r"(f[2].x), "+r"(f[2].y), "+r"(f[2].z), "+r"(f[2].w),
      "+r"(f[3].x), "+r"(f[3].y), "+r"(f[3].z), "+r"(f[3].w),
      "+r"(f[4].x), "+r"(f[4].y), "+r"(f[4].z), "+r"(f[4].w),
      "+r"(f[5].x), "+r"(f[5].y), "+r"(f[5].z), "+r"(f[5].w)
    : "l"(p0), "l"(p1), "l"(p2), "n"(kSpin) : "memory");
}
__device__ __forceinline__ void poll_o_b(uint4 (&f)[24], const uint4* p0, const uint4* p1, const uint4* p2) {
  asm volatile("{ .reg .pred q; .reg .u32 n, m; mov.u32 n, 0;\n"
    "bra.uni C;\n"
    "L:\n"
    "ld.relaxed.gpu.global.v4.u32 {%0,%1,%2,%3}, [%24+4096];\n"
    "ld.relaxed.gpu.global.v4.u32 {%4,%5,%6,%7}, [%25+4096];\n"
    "ld.relaxed.gpu.global.v4.u32 {%8,%9,%10,%11}, [%26+4096];\n"
    "ld.relaxed.gpu.global.v4.u32 {%12,%13,%14,%15}, [%24+6144];\n"
    "ld.relaxed.gpu.global.v4.u32 {%16,%17,%18,%19}, [%25+6144];\n"
    "ld.relaxed.gpu.global.v4.u32 {%20,%21,%22,%23}, [%26+6144];\n"
    "C: mov.u32 m, %%clock; or.b32 m, m, 1; min.u32 m, m, %0; min.u32 m, m, %4; min.u32 m, m, %8; min.u32 m, m, %12; min.u32 m, m, %16; min.u32 m, m, %20;\n"
    "setp.eq.u32 q, m, 0; vote.sync.any.pred q, q, 0xffffffff; add.u32 n, n, 1;\n"
    "setp.lt.and.u32 q, n, %27, q; @q bra.uni L; }"
    : "+r"(f[6].x), "+r"(f[6].y), "+r"(f[6].z), "+r"(f[6].w),
      "+r"(f[7].x), "+r"(f[7].y), "+r"(f[7].z), "+r"(f[7].w),
      "+r"(f[8].x), "+r"(f[8].y), "+r"(f[8].z), "+r"(f[8].w),
      "+r"(f[9].x), "+r"(f[9].y), "+r"(f[9].z), "+r"(f[9].w),
      "+r"(f[10].x), "+r"(f[10].y), "+r"(f[10].z), "+r"(f[10].w),
      "+r"(f[11].x), "+r"(f[11].y), "+r"(f[11].z), "+r"(f[11].w)
    : "l"(p0), "l"(p1), "l"(p2), "n"(kSpin) : "memory");
}
__device__ __forceinline__ void poll_o_c(uint4 (&f)[24], const uint4* p0, const uint4* p1, const uint4* p2) {
  asm volatile("{ .reg .pred q; .reg .u32 n, m; mov.u32 n, 0;\n"
    "bra.uni C;\n"
    "L:\n"
    "ld.relaxed.gpu.global.v4.u32 {%0,%1,%2,%3}, [%24+8192];\n"
    "ld.relaxed.gpu.global.v4.u32 {%4,%5,%6,%7}, [%25+8192];\n"
    "ld.relaxed.gpu.global.v4.u32 {%8,%9,%10,%11}, [%26+8192];\n"
    "ld.relaxed.gpu.global.v4.u32 {%12,%13,%14,%15}, [%24+10240];\n"
    "ld.relaxed.gpu.global.v4.u32 {%16,%17,%18,%19}, [%25+10240];\n"
    "ld.relaxed.gpu.global.v4.u32 {%20,%21,%22,%23}, [%26+10240];\n"
    "C: mov.u32 m, %%clock; or.b32 m, m, 1; min.u32 m, m, %0; min.u32 m, m, %4; min.u32 m, m, %8; min.u32 m, m, %12; min.u32 m, m, %16; min.u32 m, m, %20;\n"
    "setp.eq.u32 q, m, 0; vote.sync.any.pred q, q, 0xffffffff; add.u32 n, n, 1;\n"
    "setp.lt.and.u32 q, n, %27, q; @q bra.uni L; }"
    : "+r"(f[12].x), "+r"(f[12].y), "+r"(f[12].z), "+r"(f[12].w),
      "+r"(f[13].x), "+r"(f[13].y), "+r"(f[13].z), "+r"(f[13].w),
      "+r"(f[14].x), "+r"(f[14].y), "+r"(f[14].z), "+r"(f[14].w),
      "+r"(f[15].x), "+r"(f[15].y), "+r"(f[15].z), "+r"(f[15].w),
      "+r"(f[16].x), "+r"(f[16].y), "+r"(f[16].z), "+r"(f[16].w),
      "+r"(f[17].x), "+r"(f[17].y), "+r"(f[17].z), "+r"(f[17].w)
    : "l"(p0), "l"(p1), "l"(p2), "n"(kSpin) : "memory");
}
__device__ __forceinline__ void poll_o_d(uint4 (&f)[24], const uint4* p0, const uint4* p1, const uint4* p2) {
  asm volatile("{ .reg .pred q; .reg .u32 n, m; mov.u32 n, 0;\n"
    "bra.uni C;\n"
    "L:\n"
    "ld.relaxed.gpu.global.v4.u32 {%0,%1,%2,%3}, [%24+12288];\n"
    "ld.relaxed.gpu.global.v4.u32 {%4,%5,%6,%7}, [%25+12288];\n"
    "ld.relaxed.gpu.global.v4.u32 {%8,%9,%10,%11}, [%26+12288];\n"
    "ld.relaxed.gpu.global.v4.u32 {%12,%13,%14,%15}, [%24+14336];\n"
    "ld.relaxed.gpu.global.v4.u32 {%16,%17,%18,%19}, [%25+14336];\n"
    "ld.relaxed.gpu.global.v4.u32 {%20,%21,%22,%23}, [%26+14336];\n"
    "C: mov.u32 m, %%clock; or.b32 m, m, 1; min.u32 m, m, %0; min.u32 m, m, %4; min.u32 m, m, %8; min.u32 m, m, %12; min.u32 m, m, %16; min.u32 m, m, %20;\n"
    "setp.eq.u32 q, m, 0; vote.sync.any.pred q, q, 0xffffffff; add.u32 n, n, 1;\n"
    "setp.lt.and.u32 q, n, %27, q; @q bra.uni L; }"
    : "+r"(f[18].x), "+r"(f[18].y), "+r"(f[18].z), "+r"(f[18].w),
      "+r"(f[19].x), "+r"(f[19].y), "+r"(f[19].z), "+r"(f[19].w),
      "+r"(f[20].x), "+r"(f[20].y), "+r"(f[20].z), "+r"(f[20].w),
      "+r"(f[21].x), "+r"(f[21].y), "+r"(f[21].z), "+r"(f[21].w),
      "+r"(f[22].x), "+r"(f[22].y), "+r"(f[22].z), "+r"(f[22].w),
      "+r"(f[23].x), "+r"(f[23].y), "+r"(f[23].z), "+r"(f[23].w)
    : "l"(p0), "l"(p1), "l"(p2), "n"(kSpin) : "memory");
}
__device__ __forceinline__ void poll_part(uint4 (&f)[8], const uint4* p0, uint32_t bad) {
  asm volatile("{ .reg .pred q; .reg .u32 n, m; mov.u32 n, 0;\n"
    "L:\n"
    "ld.relaxed.gpu.global.v4.u32 {%0,%1,%2,%3}, [%32+0];\n"
    "ld.relaxed.gpu.global.v4.u32 {%4,%5,%6,%7}, [%32+9216];\n"
    "ld.relaxed.gpu.global.v4.u32 {%8,%9,%10,%11}, [%32+18432];\n"
    "ld.relaxed.gpu.global.v4.u32 {%12,%13,%14,%15}, [%32+27648];\n"
    "ld.relaxed.gpu.global.v4.u32 {%16,%17,%18,%19}, [%32+36864];\n"
    "ld.relaxed.gpu.global.v4.u32 {%20,%21,%22,%23}, [%32+46080];\n"
    "ld.relaxed.gpu.global.v4.u32 {%24,%25,%26,%27}, [%32+55296];\n"
    "ld.relaxed.gpu.global.v4.u32 {%28,%29,%30,%31}, [%32+64512];\n"
    "C: xor.b32 m, %0, %34; lop3.b32 m, m, %4, %34, 0x60; lop3.b32 m, m, %8, %34, 0x60; lop3.b32 m, m, %12, %34, 0x60; lop3.b32 m, m, %16, %34, 0x60; lop3.b32 m, m, %20, %34, 0x60; lop3.b32 m, m, %24, %34, 0x60; lop3.b32 m, m, %28, %34, 0x60; and.b32 m, m, 1;\n"
    "setp.eq.u32 q, m, 0; vote.sync.any.pred q, q, 0xffffffff; add.u32 n, n, 1;\n"
    "setp.lt.and.u32 q, n, %33, q; @q bra.uni L; }"
    : "=&r"(f[0].x), "=&r"(f[0].y), "=&r"(f[0].z), "=&r"(f[0].w),
      "=&r"(f[1].x), "=&r"(f[1].y), "=&r"(f[1].z), "=&r"(f[1].w),
      "=&r"(f[2].x), "=&r"(f[2].y), "=&r"(f[2].z), "=&r"(f[2].w),
      "=&r"(f[3].x), "=&r"(f[3].y), "=&r"(f[3].z), "=&r"(f[3].w),
      "=&r"(f[4].x), "=&r"(f[4].y), "=&r"(f[4].z), "=&r"(f[4].w),
      "=&r"(f[5].x), "=&r"(f[5].y), "=&r"(f[5].z), "=&r"(f[5].w),
      "=&r"(f[6].x), "=&r"(f[6].y), "=&r"(f[6].z), "=&r"(f[6].w),
      "=&r"(f[7].x), "=&r"(f[7].y), "=&r"(f[7].z), "=&r"(f[7].w)
    : "l"(p0), "n"(kSpin), "r"(bad) : "memory");
}
__device__ __forceinline__ void poll_fin(uint4 (&f)[8], const uint4* p0, uint32_t bad) {
  asm volatile("{ .reg .pred q; .reg .u32 n, m; mov.u32 n, 0;\n"
    "L:\n"
    "ld.relaxed.gpu.global.v4.u32 {%0,%1,%2,%3}, [%32+0];\n"
    "ld.relaxed.gpu.global.v4.u32 {%4,%5,%6,%7}, [%32+512];\n"
    "ld.relaxed.gpu.global.v4.u32 {%8,%9,%10,%11}, [%32+1024];\n"
    "ld.relaxed.gpu.global.v4.u32 {%12,%13,%14,%15}, [%32+1536];\n"
    "ld.relaxed.gpu.global.v4.u32 {%16,%17,%18,%19}, [%32+2048];\n"
    "ld.relaxed.gpu.global.v4.u32 {%20,%21,%22,%23}, [%32+2560];\n"
    "ld.relaxed.gpu.global.v4.u32 {%24,%25,%26,%27}, [%32+3072];\n"
    "ld.relaxed.gpu.global.v4.u32 {%28,%29,%30,%31}, [%32+3584];\n"
    "C: xor.b32 m, %0, %34; lop3.b32 m, m, %4, %34, 0x60; lop3.b32 m, m, %8, %34, 0x60; lop3.b32 m, m, %12, %34, 0x60; lop3.b32 m, m, %16, %34, 0x60; lop3.b32 m, m, %20, %34, 0x60; lop3.b32 m, m, %24, %34, 0x60; lop3.b32 m, m, %28, %34, 0x60; and.b32 m, m, 1;\n"
    "setp.eq.u32 q, m, 0; vote.sync.any.pred q, q, 0xffffffff; add.u32 n, n, 1;\n"
    "setp.lt.and.u32 q, n, %33, q; @q bra.uni L; }"
    : "=&r"(f[0].x), "=&r"(f[0].y), "=&r"(f[0].z), "=&r"(f[0].w),
      "=&r"(f[1].x), "=&r"(f[1].y), "=&r"(f[1].z), "=&r"(f[1].w),
      "=&r"(f[2].x), "=&r"(f[2].y), "=&r"(f[2].z), "=&r"(f[2].w),
      "=&r"(f[3].x), "=&r"(f[3].y), "=&r"(f[3].z), "=&r"(f[3].w),
      "=&r"(f[4].x), "=&r"(f[4].y), "=&r"(f[4].z), "=&r"(f[4].w),
      "=&r"(f[5].x), "=&r"(f[5].y), "=&r"(f[5].z), "=&r"(f[5].w),
      "=&r"(f[6].x), "=&r"(f[6].y), "=&r"(f[6].z), "=&r"(f[6].w),
      "=&r"(f[7].x), "=&r"(f[7].y), "=&r"(f[7].z), "=&r"(f[7].w)
    : "l"(p0), "n"(kSpin), "r"(bad) : "memory");
}

__device__ __forceinline__ void mma16816(float (&c)[4], uint32_t a0, uint32_t a1, uint32_t a2, uint32_t a3, uint32_t b0, uint32_t b1) {
  asm("mma.sync.aligned.m16n8k16.row.col.f32.bf16.bf16.f32 {%0,%1,%2,%3}, {%4,%5,%6,%7}, {%8,%9}, {%0,%1,%2,%3};"
      : "+f"(c[0]), "+f"(c[1]), "+f"(c[2]), "+f"(c[3]) : "r"(a0), "r"(a1), "r"(a2), "r"(a3), "r"(b0), "r"(b1));
}
__device__ __forceinline__ uint32_t pack2(float lo, float hi) {
  uint32_t r;
  asm("cvt.rn.bf16x2.f32 %0, %1, %2;" : "=r"(r) : "f"(hi), "f"(lo));
  return r;
}
__device__ __forceinline__ uint32_t transpose8x8(uint32_t a) {
  uint32_t d;
  asm volatile("movmatrix.sync.aligned.m8n8.trans.b16 %0, %1;" : "=r"(d) : "r"(a));
  return d;
}
__device__ __forceinline__ float ex2(float t) {
  float e;
  asm("ex2.approx.ftz.f32 %0, %1;" : "=f"(e) : "f"(t));
  return e;
}
__device__ __forceinline__ float rcp(float t) {
  float e;
  asm("rcp.approx.ftz.f32 %0, %1;" : "=f"(e) : "f"(t));
  return e;
}
template <uint32_t C>
__device__ __forceinline__ uint32_t pinned() {
  uint32_t v;
  asm volatile("{ .reg .u32 t; mov.u32 t, %%clock; or.b32 t, t, 0x40000000; min.u32 %0, t, %1; }" : "=r"(v) : "n"(C) : "memory");
  return v;
}
__device__ __forceinline__ uint32_t phi2(float t0, float t1, float l2e = 1.4426950408889634f) {
  uint32_t m, e = pack2(ex2(t0 * l2e), ex2(t1 * l2e));
  asm("cvt.rn.relu.bf16x2.f32 %0, %1, %2;" : "=r"(m) : "f"(t1), "f"(t0));
  asm("min.bf16x2 %0, %0, %1;" : "+r"(e) : "r"(0x3f803f80u));
  asm("add.rn.bf16x2 %0, %0, %1;" : "+r"(e) : "r"(m));
  asm("add.rn.bf16x2 %0, %0, %1;" : "+r"(e) : "r"(0x35863586u));
  return e;
}
__device__ __forceinline__ uint32_t mul2(uint32_t a, uint32_t b) {
  uint32_t r;
  asm("mul.rn.bf16x2 %0, %1, %2;" : "=r"(r) : "r"(a), "r"(b));
  return r;
}
__device__ __forceinline__ void st_x16(uint4* p, uint32_t a, uint32_t b, uint32_t c, uint32_t d) {
  asm volatile("st.relaxed.gpu.global.v4.u32 [%0], {%1, %2, %3, %4};" ::"l"(p), "r"(a), "r"(b), "r"(c), "r"(d) : "memory");
}
__device__ __forceinline__ void st_tag(uint4* p, const float (&v)[4], uint32_t tag) {
  st_x16(p, (__float_as_uint(v[0]) & ~1u) | tag, __float_as_uint(v[1]), __float_as_uint(v[2]), __float_as_uint(v[3]));
}
__device__ __forceinline__ void wait_flag(const unsigned* p, unsigned val) {
  unsigned v;
  int n = 0;
  do {
    asm volatile("ld.acquire.gpu.global.u32 %0, [%1];" : "=r"(v) : "l"(p) : "memory");
  } while (__any_sync(~0u, v != val) && ++n < kSpin);
}
constexpr int kNld[25] = SCHED_LD;
constexpr int kSt[24] = SCHED_ST;
template <int H>
__device__ __forceinline__ void store_frag(const uint4 (&fo)[8], uint4* od) {
  if constexpr (H > 0) st_x16(od + H * 128, fo[H].x, fo[H].y, fo[H].z, fo[H].w);
}
template <int A, int B>
__device__ __forceinline__ void load_frags(uint4 (&f)[24], const uint4* p0, const uint4* p1, const uint4* p2) {
  if constexpr (A < B) {
    asm volatile("ld.relaxed.gpu.global.v4.u32 {%0,%1,%2,%3}, [%4];"
                 : "=r"(f[A].x), "=r"(f[A].y), "=r"(f[A].z), "=r"(f[A].w)
                 : "l"((A % 3 == 0 ? p0 : A % 3 == 1 ? p1 : p2) + (A / 3) * 128) : "memory");
    load_frags<A + 1, B>(f, p0, p1, p2);
  }
}
__device__ __forceinline__ float bf_lo(uint32_t v) { return __uint_as_float(v << 16); }
__device__ __forceinline__ float bf_hi(uint32_t v) { return __uint_as_float(v & 0xffff0000u); }

__global__ void __launch_bounds__(kThreads, 1)
fused_kernel(const uint4* __restrict__ x_in, const uint4* __restrict__ gate_w,
             const __grid_constant__ Ptrs PW, const __grid_constant__ Params P) {
  extern __shared__ __align__(1024) uint8_t smem[];
  const uint32_t sb = (uint32_t)__cvta_generic_to_shared(smem);
  const uint32_t bars = sb + BAR_OFF;
  const int tid = threadIdx.x, lane = tid & 31;
  const int bx = blockIdx.x;
  const int b = bx & 1, cq = bx >> 1;
  const int q7 = ((cq - 36) * 37) >> 8;
  const int gi = cq < 4 ? cq : (cq < 36 ? (cq - 4) >> 3 : q7);
  const int gg = cq < 4 ? 0 : (cq < 36 ? 1 + ((cq - 4) & 7) : cq - 27 - 7 * q7);
  const int gp = (int)(((MAPPING ? 0xFEBA763DC9854210ull : 0xFDB9753ECA864210ull) >> (4 * gg)) & 15);
  const int r = (gp & 14) + (gi >> 1), j = (gp & 1) * 2 + (gi & 1), c = b * 4 + j, id = r * 8 + c;

  if (tid == 0) {
    mbar_init(bars + 8 * B_XFULL, 1);
    mbar_init(bars + 8 * B_FULL, 1);
    mbar_expect_tx(bars + 8 * B_XFULL, UNIT);
    tma2d(sb, &P.x, 0, r * 128, bars + 8 * B_XFULL);
    mbar_expect_tx(bars + 8 * B_FULL, UNIT);
    tma3d(sb + RING * UNIT, &P.w[b], 0, 0, 8 + 2 * j, bars + 8 * B_FULL);
    TRW(9);
  }
  const int warp = __shfl_sync(~0u, tid >> 5, 0);

  if (warp >= 4) {
    if (warp < 4 + PREFETCH0 && lane < 24) {
      const char* pf = lane < 16 ? (const char*)x_in + (r * 128 + c * 16 + lane) * 1024 + (warp - 4) * 128
                                 : (const char*)PW.wqkv[b] + ((warp - 4) * 64 + r * 4 + ((lane >> 1) & 3)) * 3072 + 1024 + j * 256 + (lane & 1) * 128;
      asm volatile("prefetch.global.L2 [%0];" ::"l"(pf));
    }
    asm volatile("setmaxnreg.inc.sync.aligned.u32 224;");
    asm volatile("barrier.cluster.arrive.relaxed.aligned;" ::: "memory");
    bar_sync(14, 384);
    const int w = (warp >> 2) - 1, wq = warp & 3, t = tid & 127;
    const int g = lane >> 2;

    const uint4 zero = make_uint4(0, 0, 0, 0);
    uint4* part = &g_part[c][r][w][4 * wq + (lane >> 3)][lane & 7];
    uint4* partz = &g_part[c][r][w][4 * wq + (lane >> 3)][16 + (g & 1)];
    uint4* od = &g_obuf[r][b][w][8 * j][t];

    int slot = 0; uint32_t ph = 0;
    {
      float ak[64], av[64];
#pragma unroll 1
      for (int s = 0; s < 8; s++) {
        mbar_wait(bars + 8 * (B_XFULL + s), 0);
        mbar_wait(bars + 8 * (B_FULL + slot), ph);
        if (s == 0) TR(2);
        const uint64_t da = mkdesc(sb + (RING + slot) * UNIT + w * 8192), db = mkdesc(sb + s * UNIT);
        WG_FENCE();
#pragma unroll
        for (int kk = 0; kk < 4; kk++) wg_t(ak, da + kk * 128, db + kk * 2, kk ? 1 : s);
        WG_COMMIT();
        WG_WAIT(1);
        if (s > 0 && lane == 0) mbar_arrive(bars + 8 * (B_EMPTY + (slot ? slot - 1 : 5)));
        if (++slot == 6) { slot = 0; ph ^= 1; }
      }
      TR(1);
      mbar_wait(bars + 8 * B_EPOCH, 0);
      const uint32_t tag = *(const uint32_t*)(smem + TAG_OFF);
      uint32_t pk[32];
#pragma unroll
      for (int s = 0; s < 8; s++) {
        constexpr int kSlot0 = 8 % 6;
        const int sl = (kSlot0 + s) % 6, prev = (kSlot0 + s + 5) % 6;
        mbar_wait(bars + 8 * (B_FULL + sl), ((8 + s) / 6) & 1);
        const uint64_t da = mkdesc(sb + (RING + sl) * UNIT + w * 8192), db = mkdesc(sb + s * UNIT);
        WG_FENCE();
#pragma unroll
        for (int kk = 0; kk < 4; kk++) wg_t(av, da + kk * 128, db + kk * 2, s | kk);
        WG_COMMIT();
        WG_WAIT(1);
        if (lane == 0) mbar_arrive(bars + 8 * (B_EMPTY + prev));
        if (s == 0) reg_fence(ak);
        if (s < 7) {
          const float l2e = VPIN ? __uint_as_float(pinned<0x3FB8AA3Bu>()) : 1.4426950408889634f;
#pragma unroll
          for (int i = s ? 4 * s + 4 : 0; i < 4 * s + 8; i++) {
            pk[i] = phi2(ak[2 * i], ak[2 * i + 1], l2e);
            asm volatile("" : "+r"(pk[i]));
          }
        }
        if (s < 4) { od[2 * s * 128] = zero; od[(2 * s + 1) * 128] = zero; }
        if (s == 3) {
          __syncwarp();
          if (lane == 0) mbar_arrive(bars + 8 * B_CLR);
        }
        if (s == 5 || s == 6) st_x16(part + 8 * (s - 5), tag ^ 1, 0, 0, 0);
        if (s == 7 && (lane & 3) == 0) st_x16(partz, tag ^ 1, 0, 0, 0);
      }
      WG_WAIT(0);
      reg_fence(av);
      if (lane == 0) mbar_arrive(bars + 8 * (B_EMPTY + 3));
      TR(3);
      float c0[4] = {0.f, 0.f, 0.f, 0.f}, c1[4] = {0.f, 0.f, 0.f, 0.f}, cz[4] = {0.f, 0.f, 0.f, 0.f};
      const uint32_t ones = pinned<0x3f803f80u>();
#pragma unroll
      for (int u = 0; u < 8; u++) {
        const uint32_t a0 = pack2(av[8 * u], av[8 * u + 1]), a1 = pack2(av[8 * u + 2], av[8 * u + 3]);
        const uint32_t a2 = pack2(av[8 * u + 4], av[8 * u + 5]), a3 = pack2(av[8 * u + 6], av[8 * u + 7]);
        mma16816(cz, pk[4 * u], pk[4 * u + 1], pk[4 * u + 2], pk[4 * u + 3], ones, ones);
        mma16816(c0, a0, a1, a2, a3, pk[4 * u], pk[4 * u + 2]);
        mma16816(c1, a0, a1, a2, a3, pk[4 * u + 1], pk[4 * u + 3]);
      }
      st_tag(part, c0, tag); st_tag(part + 8, c1, tag);
      if ((lane & 3) == 0) st_tag(partz, cz, tag);
      __syncwarp();
      if (lane == 0) mbar_arrive(bars + 8 * B_E1);
      TR(4);
    }

    uint4 fo[8], f[24];
    uint32_t rem;
    asm("mapa.shared::cluster.u32 %0, %1, %2;" : "=r"(rem) : "r"(sb), "r"(1 - b));
    const int s0 = j < 1, s1 = 1 + (j < 2), s2 = 2 + (j < 3);
    const uint4* osrc = &g_obuf[r][b][w][0][t];
    const uint4 *p0 = osrc + s0 * 1024, *p1 = osrc + s1 * 1024, *p2 = osrc + s2 * 1024;
    {
      float aq[64];
      bar_sync(1, 256);
      if (QSKEW && w == 1) bar_sync(4, 256);
      slot = 4; ph = 0;
#pragma unroll 1
      for (int s = 0; s < 8; s++) {
        mbar_wait(bars + 8 * (B_FULL + slot), ph);
        const uint64_t db = mkdesc(sb + (RING + slot) * UNIT), da = mkdesc(sb + s * UNIT + w * 8192);
        WG_FENCE();
#pragma unroll
        for (int kk = 0; kk < 4; kk++) wg_q(aq, da + kk * 2, db + kk * 128, kk ? 1 : s);
        WG_COMMIT();
        if (QSKEW && w == 0 && s == QSKEW - 1) asm volatile("bar.arrive 4, 256;" ::: "memory");
        WG_WAIT(1);
        if (s > 0 && lane == 0) {
          mbar_arrive(bars + 8 * (B_EMPTY + (slot ? slot - 1 : 5)));
          if (s == 1) mbar_arrive(bars + 8 * B_XFREE);
        }
        if (++slot == 6) { slot = 0; ph ^= 1; }
      }
      asm volatile("barrier.cluster.wait.aligned;" ::: "memory");
      WG_WAIT(0);
      reg_fence(aq);
      if (t == 0) {
        mbar_expect_tx(bars + 8 * (B_PIN + w), 8192);
        asm volatile("mbarrier.arrive.shared::cluster.b64 _, [%0];" ::"r"(rem + BAR_OFF + 8 * B_PFREE) : "memory");
      }
      TR(7);
      uint32_t a[32];
#define PHI(h)                                                                        \
  _Pragma("unroll") for (int i_ = 4 * (h); i_ < 4 * (h) + 4; i_++) {                  \
    a[i_] = phi2(aq[2 * i_], aq[2 * i_ + 1]);                                         \
    asm volatile("" : "+r"(a[i_]));                                                   \
  }
#define MM(h)                                                                                       \
    float n0_##h[4] = {0.f, 0.f, 0.f, 0.f}, n1_##h[4] = {0.f, 0.f, 0.f, 0.f}, dn_##h[4] = {1e-6f, 1e-6f, 1e-6f, 1e-6f}; \
    {                                                                                               \
      const uint4 kv = *(const uint4*)(smem + KVS_OFF + (h) * 512 + lane * 16);                     \
      const uint2 zf = *(const uint2*)(smem + ZS_OFF + (h) * 256 + lane * 8);                       \
      mma16816(dn_##h, a[4 * (h)], a[4 * (h) + 1], a[4 * (h) + 2], a[4 * (h) + 3], zf.x, zf.y);     \
      mma16816(n0_##h, a[4 * (h)], a[4 * (h) + 1], a[4 * (h) + 2], a[4 * (h) + 3], kv.x, kv.y);     \
      mma16816(n1_##h, a[4 * (h)], a[4 * (h) + 1], a[4 * (h) + 2], a[4 * (h) + 3], kv.z, kv.w);     \
    }                                                                                               \
    dn_##h[0] = g0 * rcp(dn_##h[0]);                                                                \
    dn_##h[2] = g1 * rcp(dn_##h[2]);
#define FIN(h) {                                                                                    \
    fo[h] = make_uint4(pack2(n0_##h[0] * dn_##h[0], n0_##h[1] * dn_##h[0]), pack2(n0_##h[2] * dn_##h[2], n0_##h[3] * dn_##h[2]), \
                       pack2(n1_##h[0] * dn_##h[0], n1_##h[1] * dn_##h[0]), pack2(n1_##h[2] * dn_##h[2], n1_##h[3] * dn_##h[2])); \
    asm("max.u32 %0, %0, 1;" : "+r"(fo[h].x));           \
    if ((h) < NSTG) st_x16(od + (h) * 128, fo[h].x, fo[h].y, fo[h].z, fo[h].w);                     \
  }
      PHI(0); PHI(1); PHI(2); PHI(3);
      if (PREFIX > 4) PHI(4);
      if (PREFIX > 5) PHI(5);
      if (PREFIX > 6) PHI(6);
      if (PREFIX > 7) PHI(7);
      TR(5);
      mbar_wait(bars + 8 * B_KVFULL, 0);
      TR(6);
      const float g0 = ((const float*)(smem + GS_OFF))[w * 64 + wq * 16 + g], g1 = ((const float*)(smem + GS_OFF))[w * 64 + wq * 16 + g + 8];
      { MM(0) MM(1) FIN(0) FIN(1) }
      if (PREFIX <= 4) PHI(4);
      if (PREFIX <= 5) PHI(5);
      SEQ();
      { MM(2) MM(3) FIN(2) FIN(3) }
      if (PREFIX <= 6) PHI(6);
      if (PREFIX <= 7) PHI(7);
      SEQ();
      MM(4) MM(5) MM(6) MM(7)
      asm volatile("bar.arrive %0, 256;" ::"r"(2 + w), "f"(dn_4[0]), "f"(dn_5[0]), "f"(dn_6[0]), "f"(dn_7[0]) : "memory");
      FIN(4) FIN(5) FIN(6) FIN(7)
      TR(9);
    }

    float lo[32], hi[32];
    const uint64_t d0 = mkdesc(sb + UNIT);
    const uint64_t dd[3] = {d0 + s0 * 2048, d0 + s1 * 2048 + (s1 >> 1) * 3072, d0 + s2 * 2048 + 3072};
    const uint64_t dj = d0 + j * 2048 + (j >> 1) * 3072;
#define DESC(i) (dd[(i) % 3] + (((i) / 3) >> 2) * 1024 + (((i) / 3) & 3) * 128)
    mbar_wait(bars + 8 * B_WO, 0);
    bar_sync(3 - w, 256);
    TR(10);
#define STEP(n, frag, desc, sd) {                                                     \
    wg_o64(lo, frag, desc, sd);                                                       \
    wg_o64(hi, frag, (desc) + 512, sd);                                               \
    SEQ();                                                                            \
    load_frags<kNld[n], kNld[(n) + 1]>(f, p0, p1, p2);                                \
    store_frag<kSt[n]>(fo, od);                                                       \
    SEQ();                                                                            \
  }
#define OWN(h) STEP(h, fo[h], dj + ((h) >> 2) * 1024 + ((h) & 3) * 128, h)
#define REM(i) STEP(8 + (i), f[i], DESC(i), 1)
    WG_FENCE();
    OWN(0) OWN(1) OWN(2) OWN(3) OWN(4) OWN(5) OWN(6) OWN(7)
    TR(11);
    TRD(20, poll_o_a(f, p0, p1, p2));
    WG_FENCE();
    REM(0) REM(1) REM(2) REM(3) REM(4) REM(5)
    TR(12);
    TRD(21, poll_o_b(f, p0, p1, p2));
    WG_FENCE();
    REM(6) REM(7) REM(8) REM(9) REM(10) REM(11)
    TR(13);
    TRD(22, poll_o_c(f, p0, p1, p2));
    WG_FENCE();
    REM(12) REM(13) REM(14)
#pragma unroll
    for (int i = 24 - NLO; i < 18; i++) wg_o64(lo, f[i], DESC(i), 1);
    TR(14);
    TRD(23, poll_o_d(f, p0, p1, p2));
    WG_FENCE();
#pragma unroll
    for (int i = 18; i < 24; i++) wg_o64(lo, f[i], DESC(i), 1);
    WG_COMMIT();
    wg_o64(hi, f[24 - NLO], DESC(24 - NLO) + 512, 1);
    wg_o64(hi, f[25 - NLO], DESC(25 - NLO) + 512, 1);
    WG_COMMIT();
    mbar_wait(bars + 8 * B_PFREE, 0);
    TRD(29, WG_WAIT(1));
    reg_fence(lo);
    TR(15);
    const uint32_t box = 7 * UNIT + w * 8192 + t * 16;
#pragma unroll
    for (int u = 0; u < 4; u++)
      asm volatile("st.async.shared::cluster.mbarrier::complete_tx::bytes.v4.b32 [%0], {%1,%2,%3,%4}, [%5];"
                   ::"r"(rem + box + u * 2048), "r"(pack2(lo[8 * u], lo[8 * u + 1])), "r"(pack2(lo[8 * u + 2], lo[8 * u + 3])),
                     "r"(pack2(lo[8 * u + 4], lo[8 * u + 5])), "r"(pack2(lo[8 * u + 6], lo[8 * u + 7])),
                     "r"(rem + BAR_OFF + 8 * (B_PIN + w)) : "memory");
    if (HIDEFER) {
      if (w) asm volatile("bar.arrive 5, 256;" ::: "memory");
      else bar_sync(5, 256);
    }
    SEQ();
#pragma unroll
    for (int i = 26 - NLO; i < 24; i++) wg_o64(hi, f[i], DESC(i) + 512, 1);
    WG_COMMIT();
    TRD(28, mbar_wait(bars + 8 * (B_PIN + w), 0));
    uint4 pp[4];
#pragma unroll
    for (int u = 0; u < 4; u++) pp[u] = *(const uint4*)(smem + box + u * 2048);
    TR(16);
    WG_WAIT(0);
    reg_fence(hi);
    TR(17);
    const uint32_t stg = sb + 6 * UNIT + w * 8192;
    const int srow = wq * 16 + (lane & 15);
#pragma unroll
    for (int i = 0; i < 4; i++) {
      const uint32_t pw[4] = {pp[i].x, pp[i].y, pp[i].z, pp[i].w};
      uint32_t o[4];
#pragma unroll
      for (int k = 0; k < 4; k++)
        o[k] = pack2(hi[8 * i + 2 * k] + bf_lo(pw[k]), hi[8 * i + 2 * k + 1] + bf_hi(pw[k]));
      const uint32_t addr = stg + srow * 128 + (((2 * i + (lane >> 4)) ^ (srow & 7)) << 4);
      asm volatile("stmatrix.sync.aligned.m8n8.x4.shared.b16 [%0], {%1,%2,%3,%4};"
                   ::"r"(addr), "r"(o[0]), "r"(o[1]), "r"(o[2]), "r"(o[3]) : "memory");
    }
    __syncwarp();
    {
      const int row = wq * 16 + (lane >> 3), ch = lane & 7;
      uint4* po = PW.out + (r * 128 + w * 64 + row) * 64 + j * 16 + b * 8 + ch;
#pragma unroll
      for (int i = 0; i < 4; i++)
        po[i * 256] = *(const uint4*)(smem + 6 * UNIT + w * 8192 + (row + 4 * i) * 128 + ((ch ^ ((row + 4 * i) & 7)) << 4));
    }
    TR(18);
  } else {
    if (tid == 32) {
#pragma unroll
      for (int i = 1; i < B_EMPTY; i++)
        if (i != B_FULL) mbar_init(bars + 8 * i, 1);
    } else if (tid == 64) {
#pragma unroll
      for (int i = B_EMPTY; i < B_PIN + 2; i++) mbar_init(bars + 8 * i, i < B_KVFULL ? 8 : (i == B_KVFULL ? 3 : (i == B_PFREE ? 2 : 1)));
      asm volatile("fence.mbarrier_init.release.cluster;" ::: "memory");
    }
    bar_sync(13, 128);
    asm volatile("bar.arrive 14, 384;" ::: "memory");
    if (tid == 0) {
#pragma unroll 1
      for (int s = 1; s < 3; s++) {
        mbar_expect_tx(bars + 8 * (B_XFULL + s), UNIT);
        tma2d(sb + s * UNIT, &P.x, s * 64, r * 128, bars + 8 * (B_XFULL + s));
        mbar_expect_tx(bars + 8 * (B_FULL + s), UNIT);
        tma3d(sb + (RING + s) * UNIT, &P.w[b], 0, s * 64, 8 + 2 * j, bars + 8 * (B_FULL + s));
        TRW(12 + s);
      }
    }
    __syncwarp();
    asm volatile("setmaxnreg.dec.sync.aligned.u32 56;");
    asm volatile("barrier.cluster.arrive.relaxed.aligned;" ::: "memory");
    if (warp == 0) {
      if (lane == 0) {
        if (TAIL == 0) asm volatile("prefetch.tensormap [%0];" ::"l"(&P.out) : "memory");
        int slot = 3; uint32_t ph = 1;
        TRW(8);
#pragma unroll 1
        for (int seq = 3; seq < 28; seq++) {
          if (seq < 8) {
            mbar_expect_tx(bars + 8 * (B_XFULL + seq), UNIT);
            tma2d(sb + seq * UNIT, &P.x, seq * 64, r * 128, bars + 8 * (B_XFULL + seq));
          }
          if (seq >= 6) mbar_wait(bars + 8 * (B_EMPTY + slot), ph);
          if (seq < 24) {
            const uint32_t fb = bars + 8 * (B_FULL + slot);
            mbar_expect_tx(fb, UNIT);
            tma3d(sb + (RING + slot) * UNIT, &P.w[b], 0, (seq & 7) * 64, (seq < 16 ? (seq & 8) + 8 : 0) + 2 * j, fb);
          }
          if (seq < 9) TRW(12 + seq);
          if (seq >= 23) {
#pragma unroll 1
            for (int t = seq - 23 + (seq == 27 ? 3 : 0); t < 8 && t < 2 * seq - 43; t += 3) {
              const uint32_t u = sb + (t + (t < 4 ? 1 : 4)) * UNIT;
              mbar_expect_tx(bars + 8 * B_WO, UNIT);
              tma2d(u, &P.wo[b], j * 128 + (1 - b) * 64, t * 64, bars + 8 * B_WO);
              tma2d(u + 8192, &P.wo[b], j * 128 + b * 64, t * 64, bars + 8 * B_WO);
            }
          }
          if (++slot == 6) { slot = 0; ph ^= 1; }
        }
        TRW(1);
      }
    } else {
      const int k = warp - 1;
      const unsigned e1 = __ldcg(&g_clean[id * 8]) + 1u;
      const int hw = (lane >> 3) & 1, l8 = lane & 7;
      uint4* fin = k < 2 ? &g_fin[c][hw][2 * (r >> 2) + k][8 * (r & 3) + l8] : &g_fin[c][2][4 * hw + (r >> 2)][2 * (r & 3) + (l8 >> 2)];
      const bool owner = lane < 16 && (k < 2 || (lane & 3) == 0);
      const uint32_t tag = e1 & 1u;
      if (tid == 32) {
        *(uint32_t*)(smem + TAG_OFF) = tag;
        mbar_arrive(bars + 8 * B_EPOCH);
      }
      if (owner) st_x16(fin, tag ^ 1, 0, 0, 0);
      {
        uint4 u[4];
#pragma unroll
        for (int i = 0; i < 4; i++) u[i] = __ldg(gate_w + (lane & 15) + 16 * i);
#pragma unroll 1
        for (int it = 2 - k; it < 8; it += 3) {
          const int row = r * 128 + c * 16 + 2 * it + (lane >> 4);
          const uint4* px = x_in + row * 64 + (lane & 15);
          float a0 = 0.f, a1 = 0.f;
#pragma unroll
          for (int i = 0; i < 4; i++) {
            const uint4 v = __ldg(px + 16 * i);
            const uint32_t p[4] = {mul2(v.x, u[i].x), mul2(v.y, u[i].y), mul2(v.z, u[i].z), mul2(v.w, u[i].w)};
#pragma unroll
            for (int m = 0; m < 4; m++) { a0 += bf_lo(p[m]); a1 += bf_hi(p[m]); }
          }
          a0 += a1;
#pragma unroll
          for (int o = 1; o < 16; o <<= 1) a0 += __shfl_xor_sync(~0u, a0, o);
          const uint32_t v = (__float_as_uint(a0) & ~1u) | tag;
          if ((lane & 15) < 2) st_x16(&g_logit[row][lane & 1], v, v, v, v);
          if (it < 3) {
            const int ln = cq * 64 + lane;
            const char* pw = k < 2 ? (const char*)PW.wqkv[b] + (ln >> 3) * 3072 + (ln & 7) * 128 + (k ? 0 : 2048)
                                   : (const char*)PW.wo[b] + ln * 128;
            asm volatile("prefetch.global.L2 [%0];" ::"l"(pw));
            asm volatile("prefetch.global.L2 [%0];" ::"l"(pw + (k < 2 ? 4 * 3072 : 4096)));
          }
        }
      }
      float gate[2];
      mbar_wait(bars + 8 * B_CLR, 0);
      if (k == 0) {
        TRW(6);
        if (lane == 0) asm volatile("st.release.gpu.global.u32 [%0], %1;" ::"l"(&g_clean[id * 8]), "r"(e1) : "memory");
        TRW(12);
      } else {
        const uint4* lg = &g_logit[r * 128 + (k - 1) * 64 + lane][0];
        uint32_t l0, l1;
        int n = 0;
        do {
          asm volatile("ld.relaxed.gpu.global.u32 %0, [%1];" : "=r"(l0) : "l"(lg) : "memory");
          asm volatile("ld.relaxed.gpu.global.u32 %0, [%1];" : "=r"(l1) : "l"(lg + 64) : "memory");
        } while (__any_sync(~0u, ((l0 ^ tag) | (l1 ^ tag)) & 1) && ++n < kSpin);
        const float sgn = b ? 1.4426950408889634f : -1.4426950408889634f;
        gate[0] = rcp(1.f + ex2(__uint_as_float(l0) * sgn));
        gate[1] = rcp(1.f + ex2(__uint_as_float(l1) * sgn));
      }
      uint4 v[8];
      const uint4* src1 = &g_part[c][8 * (lane >> 4)][hw][r][k < 2 ? 8 * k + l8 : 16 + (l8 >> 2)];
      const uint4* src2 = &g_fin[c][k][0][k < 2 ? lane : lane >> 2];
      asm volatile("" : "+l"(src1), "+l"(src2));
      mbar_wait(bars + 8 * B_E1, 0);
      if (k == 0) TRW(2);
      poll_part(v, src1, tag ^ 1);
      if (k == 0) TRW(10);
      float s[4] = {0.f, 0.f, 0.f, 0.f};
#pragma unroll
      for (int i = 0; i < 8; i += 2) {
        s[0] += __uint_as_float(v[i].x) + __uint_as_float(v[i + 1].x);
        s[1] += __uint_as_float(v[i].y) + __uint_as_float(v[i + 1].y);
        s[2] += __uint_as_float(v[i].z) + __uint_as_float(v[i + 1].z);
        s[3] += __uint_as_float(v[i].w) + __uint_as_float(v[i + 1].w);
      }
#pragma unroll
      for (int i = 0; i < 4; i++) s[i] += __shfl_xor_sync(~0u, s[i], 16);
      if (owner) st_tag(fin, s, tag);
      if (k == 0) TRW(3);
      if (k == 2) wait_flag(&g_clean[(r * 8 + b * 4 + (lane & 3)) * 8], e1);
      poll_fin(v, src2, tag ^ 1);
      if (k == 0) TRW(4);
      mbar_wait(bars + 8 * B_XFREE, 0);
      if (k) {
        ((float*)(smem + GS_OFF))[(k - 1) * 64 + lane] = gate[0];
        ((float*)(smem + GS_OFF))[(k - 1) * 64 + lane + 32] = gate[1];
      }
      uint32_t pv[16];
#pragma unroll
      for (int i = 0; i < 8; i++) {
        pv[2 * i] = pack2(__uint_as_float(v[i].x), __uint_as_float(v[i].y));
        pv[2 * i + 1] = pack2(__uint_as_float(v[i].z), __uint_as_float(v[i].w));
      }
      if (k < 2) {
#pragma unroll
        for (int i = 0; i < 4; i++)
          *(uint4*)(smem + KVS_OFF + (4 * k + i) * 512 + lane * 16) = make_uint4(pv[4 * i], pv[4 * i + 2], pv[4 * i + 1], pv[4 * i + 3]);
      } else {
#pragma unroll
        for (int h = 0; h < 8; h++)
          *(uint2*)(smem + ZS_OFF + h * 256 + lane * 8) = make_uint2(transpose8x8(pv[2 * h]), transpose8x8(pv[2 * h + 1]));
      }
      __syncwarp();
      if (lane == 0) mbar_arrive(bars + 8 * B_KVFULL);
      if (k == 0) TRW(5);
    }
  }
}

typedef CUresult (*EncodeFn)(CUtensorMap*, CUtensorMapDataType, cuuint32_t, void*, const cuuint64_t*, const cuuint64_t*,
                             const cuuint32_t*, const cuuint32_t*, CUtensorMapInterleave, CUtensorMapSwizzle,
                             CUtensorMapL2promotion, CUtensorMapFloatOOBfill);

void encode(EncodeFn enc, CUtensorMap* m, const void* ptr, int rank, const cuuint64_t* dims, const cuuint64_t* strides,
            const cuuint32_t* box) {
  const cuuint32_t es[3] = {1, 1, 1};
  enc(m, CU_TENSOR_MAP_DATA_TYPE_BFLOAT16, rank, const_cast<void*>(ptr), dims, strides, box, es,
      CU_TENSOR_MAP_INTERLEAVE_NONE, CU_TENSOR_MAP_SWIZZLE_128B, PROMO,
      CU_TENSOR_MAP_FLOAT_OOB_FILL_NONE);
}

}

extern "C" void kernel_launch(void* const* d_in, const int* in_sizes, int n_in, void* d_out, int out_size) {
  static EncodeFn enc = nullptr;
  if (!enc) {
    void* fn = nullptr;
    cudaDriverEntryPointQueryResult qr;
    cudaGetDriverEntryPoint("cuTensorMapEncodeTiled", &fn, cudaEnableDefault, &qr);
    enc = (EncodeFn)fn;
    cudaFuncSetAttribute(fused_kernel, cudaFuncAttributeMaxDynamicSharedMemorySize, SMEM_BYTES);
  }
  Params P;
  {
    const cuuint64_t d[2] = {512, 2048}, s[1] = {1024};
    const cuuint32_t bx[2] = {64, 128}, bo[2] = {64, 64};
    encode(enc, &P.x, d_in[0], 2, d, s, bx);
    encode(enc, &P.out, d_out, 2, d, s, bo);
  }
  for (int b = 0; b < 2; b++) {
    const void* wqkv = d_in[b ? 4 : 1];
    const void* wo = d_in[b ? 5 : 2];
    const cuuint64_t d3[3] = {64, 512, 24}, s3[2] = {3072, 128};
    const cuuint32_t b3[3] = {64, 64, 2};
    encode(enc, &P.w[b], wqkv, 3, d3, s3, b3);
    const cuuint64_t d2[2] = {512, 512}, s2[1] = {1024};
    const cuuint32_t bo[2] = {64, 64};
    encode(enc, &P.wo[b], wo, 2, d2, s2, bo);
  }
  Ptrs PW = {{d_in[1], d_in[4]}, {d_in[2], d_in[5]}, (uint4*)d_out};
  cudaLaunchConfig_t cfg = {};
  cfg.gridDim = dim3(128);
  cfg.blockDim = dim3(kThreads);
  cfg.dynamicSmemBytes = SMEM_BYTES;
  cfg.stream = cudaStreamPerThread;
  cudaLaunchAttribute at[2];
  at[0].id = cudaLaunchAttributeClusterDimension;
  at[0].val.clusterDim.x = 2;
  at[0].val.clusterDim.y = 1;
  at[0].val.clusterDim.z = 1;
  at[1].id = cudaLaunchAttributeCooperative;
  at[1].val.cooperative = 1;
  cfg.attrs = at;
  cfg.numAttrs = 2;
  cudaLaunchKernelEx(&cfg, fused_kernel, (const uint4*)d_in[0], (const uint4*)d_in[6], PW, P);
}
```
